```python
import torch

def _softmax(x, axis=-1):
    return torch.softmax(x, dim=axis)
def _gelu(x):
    return torch.nn.functional.gelu(x, approximate="tanh")
def _silu(x):
    return torch.nn.functional.silu(x)
def _sigmoid(x):
    return torch.sigmoid(x)
def _layernorm(x, axis=-1, eps=1e-5):
    m = x.mean(dim=axis, keepdim=True)
    v = x.var(dim=axis, keepdim=True, unbiased=False)
    return (x - m) / torch.sqrt(v + eps)
def _scatter_add(tgt, idx, src, axis=0):
    return tgt.clone().index_add_(axis, idx, src)
def _segment_sum(src, seg, n):
    out = torch.zeros((n,) + src.shape[1:], dtype=src.dtype)
    return out.index_add_(0, seg, src)
def _pad(x, pw):
    flat = tuple(v for pair in reversed(pw) for v in pair)
    return torch.nn.functional.pad(x, flat)

kernel_name = 'standalone__mpnn_edge_mlp__graph'

def setup_inputs():

    _w = (lambda a: (lambda t: t.to(torch.bfloat16) if t.is_floating_point() else t)(torch.as_tensor(a)))
    N, deg, D, De = 25000, 16, 128, max(4, 1)
    E = N * deg
    return {
        "x": _w((lambda *s: torch.randn(*s, dtype=torch.bfloat16) * 0.05)(N, D)),
        "e_attr": _w((lambda *s: torch.randn(*s, dtype=torch.bfloat16) * 0.4)(E, De)),
        "src": _w((lambda lo, hi, *s: torch.randint(lo, hi, s))(0, N, E).to(torch.int64)),
        "dst": _w((lambda lo, hi, *s: torch.randint(lo, hi, s))(0, N, E).to(torch.int64)),
        "w_msg": _w((lambda *s: torch.randn(*s, dtype=torch.bfloat16) * 0.4)(2 * D + De, D)),
        "w_upd": _w((lambda *s: torch.randn(*s, dtype=torch.bfloat16) * 0.05)(2 * D, D)),
    }

def reference(x, e_attr, src, dst, w_msg, w_upd):
    N, D = x.shape
    m_in = torch.concatenate([x[src], x[dst], e_attr], axis=-1)
    msg = _silu(m_in @ w_msg)
    agg = _segment_sum(msg, dst, N)
    return _silu(torch.concatenate([x, agg], axis=-1) @ w_upd)
```

```cpp
#include <cuda_runtime.h>
#include <cuda_bf16.h>
#include <cuda.h>
#include <stdint.h>

namespace {

constexpr int N_NODES = 25000;
constexpr int N_EDGES = 400000;
constexpr int NCTA    = 132;
constexpr int TILE    = 190;
constexpr int CHUNK   = 3032;
constexpr int CT      = 384;
constexpr int THREADS = 512;
constexpr int LCAP    = 36;
constexpr int XCAP    = 64;
constexpr int LA = 5, LB = 3, M2 = 1, KE = 4, KP = 4, KS = 2, KI = 12, KR = 20, KA = 28;
constexpr int STAG    = 250;
constexpr int NF = 3, PW = 216;
constexpr int KS_     = 108;

constexpr uint32_t sb = 1024;
constexpr int HALF   = 192 * 128;
constexpr int SM_X   = 0;
constexpr int SM_Q   = 2 * HALF;
constexpr int SM_W   = 4 * HALF;
constexpr int SM_K   = SM_W + 65536;
constexpr int SM_L   = SM_K + 192 * KS_;
constexpr int L_X    = NCTA * LCAP * 8;
constexpr int L_PAD  = L_X + XCAP * 8;
constexpr int SM_W3  = SM_L + L_PAD + 128;
constexpr int SM_WF  = SM_W3 + 1024;
constexpr int SM_CNT = SM_WF + 1024;
constexpr int SM_HIS = SM_CNT + 1024;
constexpr int SM_DH  = SM_HIS + 640;
constexpr int SM_GM  = SM_DH + 256;
constexpr int SM_ORD = SM_GM + 128;
constexpr int SM_TR  = SM_ORD + 192;
constexpr int SM_MB  = SM_TR + 448;
constexpr int SM_TOTAL = SM_MB + 144;
static_assert(SM_TOTAL <= 232448 && SM_L % 128 == 0 && SM_ORD - SM_CNT == 2048, "smem");

constexpr int G_OVF = NCTA * NCTA * 12;

enum { BAR_C = 1, BAR_R = 2, BAR_STG = 3, BAR_P = 4, BAR_N = 7, BAR_H = 9, BAR_S = 10, BAR_T = 11, BAR_O = 13 };

constexpr unsigned long long pack5(const int (&v)[12]) {
    unsigned long long r = 0;
    for (int i = 0; i < 12; i++) r |= (unsigned long long)v[i] << (5 * i);
    return r;
}
constexpr unsigned long long SLOT_LO = pack5({23, 22, 18, 7, 11, 20, 13, 9, 3, 1, 5, 4});
constexpr unsigned long long SLOT_HI = pack5({0, 8, 2, 19, 12, 6, 10, 16, 15, 17, 21, 14});
constexpr unsigned long long WARP_END = pack5({2, 4, 6, 8, 10, 12, 14, 17, 19, 21, 23, 24});

__device__ __align__(1024) uint4 g_P[(N_NODES + NCTA) * 16];
__device__ __align__(1024) uint4 g_rec[G_OVF + NCTA * 32];
__device__ __align__(128) uint32_t g_bar[(1 + NCTA) * 32];

__device__ __forceinline__ uint32_t pack_bf16(float lo, float hi) {
    uint32_t r; asm("cvt.rn.bf16x2.f32 %0, %1, %2;" : "=r"(r) : "f"(hi), "f"(lo)); return r;
}
__device__ __forceinline__ uint32_t pack_half(float lo, float hi) {
    uint32_t r; asm("{.reg .b32 v; cvt.rn.bf16x2.f32 v, %1, %2; mul.rn.bf16x2 %0, v, %3;}" : "=r"(r) : "f"(hi), "f"(lo), "r"(0x3F003F00u)); return r;
}
__device__ __forceinline__ float tanh_a(float h) { float t; asm volatile("tanh.approx.f32 %0, %1;" : "=f"(t) : "f"(h)); return t; }
__device__ __forceinline__ float silu_half(float h) {
    float t; asm("tanh.approx.f32 %0, %1;" : "=f"(t) : "f"(h)); return fmaf(h, t, h);
}
__device__ __forceinline__ void mma8(float* d, uint32_t a0, uint32_t a1, uint32_t b0, const float* c) {
    asm volatile("mma.sync.aligned.m16n8k8.row.col.f32.bf16.bf16.f32 {%0,%1,%2,%3}, {%4,%5}, {%6}, {%7,%8,%9,%10};"
        : "=f"(d[0]), "=f"(d[1]), "=f"(d[2]), "=f"(d[3]) : "r"(a0), "r"(a1), "r"(b0), "f"(c[0]), "f"(c[1]), "f"(c[2]), "f"(c[3]));
}
__device__ __forceinline__ uint4 ldg128(const void* p) {
    uint4 v; asm volatile("ld.global.v4.u32 {%0,%1,%2,%3}, [%4];" : "=r"(v.x), "=r"(v.y), "=r"(v.z), "=r"(v.w) : "l"(p)); return v;
}
__device__ __forceinline__ uint4 lds128(uint32_t a) {
    uint4 v; asm volatile("ld.shared.v4.u32 {%0,%1,%2,%3}, [%4];" : "=r"(v.x), "=r"(v.y), "=r"(v.z), "=r"(v.w) : "r"(a)); return v;
}
__device__ __forceinline__ uint4 ldg128_nc(const void* p) {
    uint4 v; asm volatile("ld.global.nc.v4.u32 {%0,%1,%2,%3}, [%4];" : "=r"(v.x), "=r"(v.y), "=r"(v.z), "=r"(v.w) : "l"(p)); return v;
}
__device__ __forceinline__ void sts64(uint32_t a, uint32_t x, uint32_t y) {
    asm volatile("st.shared.v2.u32 [%0], {%1,%2};" :: "r"(a), "r"(x), "r"(y) : "memory");
}
__device__ __forceinline__ uint32_t lds32(uint32_t a) {
    uint32_t v; asm volatile("ld.shared.u32 %0, [%1];" : "=r"(v) : "r"(a)); return v;
}
__device__ __forceinline__ void sts128(uint32_t a, uint4 v) {
    asm volatile("st.shared.v4.u32 [%0], {%1,%2,%3,%4};" :: "r"(a), "r"(v.x), "r"(v.y), "r"(v.z), "r"(v.w) : "memory");
}
__device__ __forceinline__ void mbar_init(uint32_t mb, uint32_t cnt) {
    asm volatile("mbarrier.init.shared::cta.b64 [%0], %1;" :: "r"(mb), "r"(cnt) : "memory");
}
__device__ __forceinline__ void mbar_expect(uint32_t mb, uint32_t bytes) {
    asm volatile("mbarrier.arrive.expect_tx.shared::cta.b64 _, [%0], %1;" :: "r"(mb), "r"(bytes) : "memory");
}
__device__ __forceinline__ void mbar_arrive(uint32_t mb) {
    asm volatile("mbarrier.arrive.shared::cta.b64 _, [%0];" :: "r"(mb) : "memory");
}
__device__ __forceinline__ void mbar_wait(uint32_t mb, uint32_t parity) {
    #pragma unroll 1
    for (int it = 0; it < (1 << 22); it++) {
        uint32_t ok;
        asm volatile("{.reg .pred p; mbarrier.try_wait.parity.shared::cta.b64 p, [%1], %2; selp.u32 %0, 1, 0, p;}"
                     : "=r"(ok) : "r"(mb), "r"(parity) : "memory");
        if (ok) return;
    }
    __trap();
}
__device__ __forceinline__ bool elect() {
    uint32_t r;
    asm volatile("{.reg .pred p; elect.sync _|p, 0xffffffff; selp.u32 %0, 1, 0, p;}" : "=r"(r));
    return r;
}
__device__ __forceinline__ void tma_load(uint32_t dst, const CUtensorMap* map, int c0, int c1, uint32_t mb) {
    asm volatile("cp.async.bulk.tensor.2d.shared::cluster.global.mbarrier::complete_tx::bytes [%0], [%1, {%3, %4}], [%2];"
        :: "r"(dst), "l"((uint64_t)map), "r"(mb), "r"(c0), "r"(c1) : "memory");
}
__device__ __forceinline__ void tma_store(const CUtensorMap* map, int c0, int c1, uint32_t src) {
    asm volatile("cp.async.bulk.tensor.2d.global.shared::cta.bulk_group [%0, {%2, %3}], [%1];"
        :: "l"((uint64_t)map), "r"(src), "r"(c0), "r"(c1) : "memory");
}
__device__ __forceinline__ void load_w(uint32_t dst, const CUtensorMap* map, int row, uint32_t mb) {
    mbar_expect(mb, 32768);
    tma_load(dst, map, 0, row, mb);
    tma_load(dst + 16384, map, 64, row, mb);
}
__device__ __forceinline__ void bar_sync(int id, int n)   { asm volatile("bar.sync %0, %1;" :: "r"(id), "r"(n) : "memory"); }
__device__ __forceinline__ void bar_arrive(int id, int n) { asm volatile("bar.arrive %0, %1;" :: "r"(id), "r"(n) : "memory"); }
__device__ __forceinline__ void fence_async_smem() { asm volatile("fence.proxy.async.shared::cta;" ::: "memory"); }
__device__ __forceinline__ void publish_fence() {
    asm volatile("fence.proxy.async.global;" ::: "memory");
    asm volatile("fence.acq_rel.gpu;" ::: "memory");
}
__device__ __forceinline__ void bulk_store(const void* to, uint32_t from, uint32_t bytes) {
    asm volatile("cp.async.bulk.global.shared::cta.bulk_group [%0], [%1], %2;" :: "l"(to), "r"(from), "r"(bytes) : "memory");
}
__device__ __forceinline__ void bulk_load(uint32_t to, const void* from, uint32_t bytes, uint32_t mb) {
    mbar_expect(mb, bytes);
    asm volatile("cp.async.bulk.shared::cluster.global.mbarrier::complete_tx::bytes [%0], [%1], %2, [%3];"
        :: "r"(to), "l"(from), "r"(bytes), "r"(mb) : "memory");
}
__device__ __forceinline__ void bulk_wait() {
    asm volatile("cp.async.bulk.commit_group;" ::: "memory");
    asm volatile("cp.async.bulk.wait_group 0;" ::: "memory");
}
__device__ __forceinline__ uint32_t atoms_add(uint32_t a, uint32_t n) {
    uint32_t v; asm volatile("atom.shared.add.u32 %0, [%1], %2;" : "=r"(v) : "r"(a), "r"(n) : "memory"); return v;
}
__device__ __forceinline__ uint32_t lds8(uint32_t a) {
    uint32_t v; asm volatile("ld.shared.u8 %0, [%1];" : "=r"(v) : "r"(a)); return v;
}
__device__ __forceinline__ void sts32(uint32_t a, uint32_t v) { asm volatile("st.shared.u32 [%0], %1;" :: "r"(a), "r"(v) : "memory"); }
__device__ __forceinline__ void sched_fence() { asm volatile("pmevent 1;"); }

#define WG_D8(o) "+f"(d[o]), "+f"(d[o+1]), "+f"(d[o+2]), "+f"(d[o+3]), "+f"(d[o+4]), "+f"(d[o+5]), "+f"(d[o+6]), "+f"(d[o+7])
template <uint32_t B_BASE>
__device__ __forceinline__ void gemm128(float (&d)[64], const uint32_t (&a)[32]) {
    asm volatile("wgmma.fence.sync.aligned;" ::: "memory");
    #pragma unroll
    for (int k = 0; k < 8; k++)
        asm volatile("{.reg .pred p; setp.ne.b32 p, %69, 0;\n"
            "wgmma.mma_async.sync.aligned.m64n128k16.f32.bf16.bf16 "
            "{%0,%1,%2,%3,%4,%5,%6,%7,%8,%9,%10,%11,%12,%13,%14,%15,%16,%17,%18,%19,%20,%21,%22,%23,%24,%25,%26,%27,%28,%29,%30,%31,"
            "%32,%33,%34,%35,%36,%37,%38,%39,%40,%41,%42,%43,%44,%45,%46,%47,%48,%49,%50,%51,%52,%53,%54,%55,%56,%57,%58,%59,%60,%61,%62,%63},"
            " {%64,%65,%66,%67}, %68, p, 1, 1, 1;}"
            : WG_D8(0), WG_D8(8), WG_D8(16), WG_D8(24), WG_D8(32), WG_D8(40), WG_D8(48), WG_D8(56)
            : "r"(a[4 * k]), "r"(a[4 * k + 1]), "r"(a[4 * k + 2]), "r"(a[4 * k + 3]),
              "l"(0x4000004004000000ull + (B_BASE >> 4) + k * 128), "r"(k));
    asm volatile("wgmma.commit_group.sync.aligned;" ::: "memory");
}
__device__ __forceinline__ void load_frag(uint32_t (&a)[32], uint32_t tile, uint32_t row) {
    #pragma unroll
    for (int j = 0; j < 8; j++)
        asm volatile("ldmatrix.sync.aligned.m8n8.x4.shared.b16 {%0,%1,%2,%3}, [%4];"
            : "=r"(a[4 * j]), "=r"(a[4 * j + 1]), "=r"(a[4 * j + 2]), "=r"(a[4 * j + 3]) : "r"((row ^ ((j & 3) << 5)) + tile + (j >> 2) * HALF) : "memory");
}
template <uint32_t B_BASE>
__device__ __forceinline__ void gemm64(float (&d)[32], const uint32_t (&a)[32]) {
    #pragma unroll
    for (int k = 0; k < 8; k++)
        asm volatile("{\n"
            "wgmma.mma_async.sync.aligned.m64n64k16.f32.bf16.bf16 "
            "{%0,%1,%2,%3,%4,%5,%6,%7,%8,%9,%10,%11,%12,%13,%14,%15,%16,%17,%18,%19,%20,%21,%22,%23,%24,%25,%26,%27,%28,%29,%30,%31},"
            " {%32,%33,%34,%35}, %36, 1, 1, 1, 1;}"
            : WG_D8(0), WG_D8(8), WG_D8(16), WG_D8(24)
            : "r"(a[4 * k]), "r"(a[4 * k + 1]), "r"(a[4 * k + 2]), "r"(a[4 * k + 3]),
              "l"(0x4000004004000000ull + (B_BASE >> 4) + k * 128));
    asm volatile("wgmma.commit_group.sync.aligned;" ::: "memory");
}
template <int N> __device__ __forceinline__ void wg_wait32(float (&d)[32]) {
    asm volatile("wgmma.wait_group.sync.aligned %32;" : WG_D8(0), WG_D8(8), WG_D8(16), WG_D8(24) : "n"(N) : "memory");
}
__device__ __forceinline__ void sts8(uint32_t a, uint32_t v) { asm volatile("st.shared.u8 [%0], %1;" :: "r"(a), "r"(v) : "memory"); }
__device__ __forceinline__ void sts16(uint32_t a, uint32_t v) { asm volatile("st.shared.u16 [%0], %1;" :: "r"(a), "h"((unsigned short)v) : "memory"); }
__device__ __forceinline__ uint32_t lds16(uint32_t a) {
    uint32_t v; asm volatile("ld.shared.u16 %0, [%1];" : "=r"(v) : "r"(a)); return v;
}
__device__ __forceinline__ void wg_fence()  { asm volatile("wgmma.fence.sync.aligned;" ::: "memory"); }
__device__ __forceinline__ void wg_wait(float (&d)[64]) {
    asm volatile("wgmma.wait_group.sync.aligned 0;"
        : WG_D8(0), WG_D8(8), WG_D8(16), WG_D8(24), WG_D8(32), WG_D8(40), WG_D8(48), WG_D8(56) :: "memory");
}
__device__ __forceinline__ void store_frag(uint32_t tile, uint32_t row, const uint32_t (&r)[32], uint32_t half = HALF) {
    #pragma unroll
    for (int j = 0; j < 8; j++)
        asm volatile("stmatrix.sync.aligned.m8n8.x4.shared.b16 [%0], {%1,%2,%3,%4};"
            :: "r"((row ^ ((j & 3) << 5)) + tile + (j >> 2) * half), "r"(r[4 * j]), "r"(r[4 * j + 1]), "r"(r[4 * j + 2]), "r"(r[4 * j + 3]) : "memory");
}

__global__ void __launch_bounds__(THREADS, 1)
mpnn_kernel(const int4* __restrict__ dst, const int4* __restrict__ src, const char* __restrict__ ea,
            const unsigned short* __restrict__ w3g, uint4* __restrict__ out,
            char* gP, uint4* gRec, uint32_t* gBar,
            const __grid_constant__ CUtensorMap mapX, const __grid_constant__ CUtensorMap mapP,
            const __grid_constant__ CUtensorMap mapWm, const __grid_constant__ CUtensorMap mapWu,
            const __grid_constant__ CUtensorMap mapL) {
    extern __shared__ __align__(1024) uint8_t smem[];
    const int tid = threadIdx.x, lane = tid & 31;
    const int warp = tid >> 5;
    const int cta = blockIdx.x;
    const int node0 = cta * TILE;
    constexpr uint32_t mbX = sb + SM_MB, mbW1 = mbX + 24, mbF = mbX + 32, mbB = mbX + 56, mbR = mbX + 64,
                   mbW2 = mbX + 72, mbU = mbX + 80, mbN = mbX + 88, mbG = mbX + 96, mbV = mbX + 104;
    if (tid == CT) asm volatile("cp.async.ca.shared.global [%0], [%1], 4;" :: "r"(sb + SM_MB + 128), "l"(gBar + (1 + cta) * 32) : "memory");
    const bool v1 = tid + CT < (min(CHUNK, N_EDGES - cta * CHUNK) >> 2);
    const int i0 = cta * (CHUNK / 4) + tid, i1 = v1 ? i0 + CT : i0;
    uint4 d0, d1, s0, s1;
    if (warp < 12) {
        d0 = ldg128_nc(dst + i0); d1 = ldg128_nc(dst + i1); s0 = ldg128_nc(src + i0); s1 = ldg128_nc(src + i1);
        sched_fence();
        const uint32_t empty = (((tid % 12) + (cta & 7) * 12) & 31) * 0x010101u | 0xc0e0c0u;
        #pragma unroll
        for (int k = 0; k < 5; k++)
            if (k < 4 || tid < 80) sts128(sb + SM_L + (tid + k * CT) * 16, make_uint4(0, ~0u, 0, empty));
    } else {
        if (tid == CT + 64) { mbar_init(mbX, 1); mbar_init(mbX + 8, 1); mbar_init(mbX + 16, 1); mbar_init(mbW1, 1); mbar_init(mbV, 1); }
        if (tid == CT + 32) { mbar_init(mbF, 1); mbar_init(mbF + 8, 1); mbar_init(mbF + 16, 1); mbar_init(mbB, 1); }
        if (tid == CT + 96) { mbar_init(mbR, 1); mbar_init(mbW2, 2); mbar_init(mbU, 1); mbar_init(mbN, 15); mbar_init(mbG, 12); }
        const int i = tid - CT;
        const uint32_t c0 = i < 48 ? sb + SM_K + i * (4 * KS_) : i < 64 ? sb + SM_TR + (i & 7) * 16 : 0, cs = i < 48 ? KS_ : i < 64 ? 4 : 0;
        sts128(sb + SM_CNT + i * 16, make_uint4(c0, c0 + cs, c0 + 2 * cs, c0 + 3 * cs));
    }
    sched_fence();
    __syncthreads();

    if (warp >= 12) {
        asm volatile("setmaxnreg.dec.sync.aligned.u32 32;");
        if ((uint32_t)__cvta_generic_to_shared(smem) != sb) __trap();
        const int ht = tid - CT;
        if (warp == 14) {
            auto load_x = [&](int j) {
                mbar_expect(mbX + 8 * j, 16384);
                tma_load(sb + SM_X + j * 8192, &mapX, 0, node0 + 64 * j, mbX + 8 * j);
                tma_load(sb + SM_X + HALF + j * 8192, &mapX, 64, node0 + 64 * j, mbX + 8 * j);
            };
            if (elect()) {
                fence_async_smem();
                load_w(sb + SM_Q, &mapWm, 0, mbW1);
                #pragma unroll 1
                for (int j = 0; j < 2; j++) load_x(j);
                load_w(sb + SM_W + 32768, &mapWu, 0, mbV);
            }
            __syncwarp();
            bar_sync(BAR_R, CT + 32);
            if (elect()) {
                load_x(2);
                load_w(sb + SM_W, &mapWm, 128, mbW2);
                bulk_load(sb + SM_W3, w3g, 1024, mbW2);
            }
            __syncwarp();
            mbar_wait(mbW2, 0);
            #pragma unroll 1
            for (int m = 0; m < 8; m++) {
                const uint32_t w = sb + SM_W3 + 2 * ((lane & 1) * 256 + 32 * (m >> 1) + (lane & 24) + 4 * (m & 1) + ((lane >> 2) & 1) + (lane & 2));
                uint32_t b;
                asm volatile("mul.rn.bf16x2 %0, %1, %2;" : "=r"(b) : "r"(lds16(w) | lds16(w + 256) << 16), "r"(0x3F003F00u));
                sts32(sb + SM_WF + (m >> 2) * 512 + lane * 16 + (m & 3) * 4, b);
            }
        } else {
            const uint32_t fill = sb + (warp == 15 ? ht - 32 : ht) * 16;
            asm volatile("cp.async.wait_all;" ::: "memory");
            bar_sync(BAR_H, 96);
            const uint32_t epoch = lds32(sb + SM_MB + 128);
            if (ht == 0) gBar[(1 + cta) * 32] = epoch + 1;
            const uint32_t tag = epoch % 127 + 1;
            #pragma unroll
            for (int i = 0; i < 17; i++)
                if (i < 16 || fill < sb + 80 * 16) sts8(fill + SM_L + 15 + i * 1536, tag);
            if (ht == 0) { sts32(sb + SM_GM + 116, tag << 24); sts64(sb + SM_L + L_PAD, (N_NODES + cta) << 8, cta * (CHUNK * 8)); }
            #pragma unroll
            for (int i = 0; i < 14; i++)
                if (i < 13 || ht < 48) sts128(fill + SM_K + i * 1536, make_uint4(L_PAD * 0x10001u, L_PAD * 0x10001u, L_PAD * 0x10001u, L_PAD * 0x10001u));
            static_assert(192 * KS_ == 13 * 1536 + 48 * 16, "fill");
            const uint32_t target = (epoch + 1) * NCTA;
            if (warp == 12) {
                bar_sync(BAR_STG, CT + 96);
                #pragma unroll
                for (int c = lane; c < 160; c += 32)
                    if (lds32(sb + SM_HIS + c * 4) > (c < NCTA ? LCAP : 32)) sts8(sb + SM_L + c * 192 + 15, tag | 128);
                __syncwarp();
                if (elect()) {
                    fence_async_smem();
                    tma_store(&mapL, cta * 48, 0, sb + SM_L);
                    bulk_store(gRec + G_OVF + cta * 32, sb + SM_L + NCTA * 192, 512);
                    bulk_wait();
                    mbar_arrive(mbR);
                }
                __syncwarp();
            } else {
                bar_arrive(BAR_STG, CT + 96);
                if (warp == 15) {
                    if (lane < 16) ((uint4*)gP)[(N_NODES + cta) * 16 + lane] = make_uint4(0xF180F180u, 0xF180F180u, 0xF180F180u, 0xF180F180u);
                    __syncwarp();
                    #pragma unroll 1
                    for (int j = 0; j < 3; j++) {
                        bar_sync(BAR_P + j, 160);
                        if (elect()) {
                            fence_async_smem();
                            tma_store(&mapP, 0, node0 + 64 * j, j == 2 ? sb + SM_Q + 32768 : sb + SM_X + j * 8192);
                            tma_store(&mapP, 64, node0 + 64 * j, j == 2 ? sb + SM_Q + 40960 : sb + SM_X + HALF + j * 8192);
                            bulk_wait();
                            mbar_arrive(mbF + 8 * j);
                            if (j == 2) publish_fence();
                        }
                        __syncwarp();
                    }
                    if (elect()) {
                        asm volatile("red.relaxed.gpu.global.add.u32 [%0], 1;" :: "l"(gBar) : "memory");
                        asm volatile("cp.async.bulk.prefetch.L2.global [%0], %1;"
                            :: "l"(ea + cta * (CHUNK * 8)), "r"(min(CHUNK, N_EDGES - cta * CHUNK) * 8) : "memory");
                        #pragma unroll 1
                        for (int it = 0;; it++) {
                            uint32_t v;
                            asm volatile("ld.acquire.gpu.global.u32 %0, [%1];" : "=r"(v) : "l"(gBar) : "memory");
                            if ((int32_t)(v - target) >= 0) break;
                            if (it > (1 << 22)) __trap();
                        }
                        mbar_arrive(mbB);
                    }
                }
            }
        }
        if (warp != 15) {
            const int myslot = (int)((lane < 12 ? SLOT_LO >> (5 * lane) : SLOT_HI >> (5 * lane - 60)) & 31);
            bar_sync(BAR_N, CT + 96);
            int key[2], pos[2];
            #pragma unroll
            for (int i = 0; i < 2; i++) {
                key[i] = 63 - min((lds32(sb + SM_CNT + (ht + 96 * i) * 4) - (sb + SM_K + (ht + 96 * i) * KS_)) >> 1, 63u);
                pos[i] = atoms_add(sb + SM_DH + 4 * key[i], 1);
            }
            bar_sync(BAR_S, 96);
            const uint4 h = lds128(sb + SM_DH + 16 * (lane & 15));
            const uint32_t a1 = h.x + h.y, a2 = a1 + h.z, a3 = a2 + h.w;
            const uint32_t u1 = __shfl_up_sync(~0u, a3, 1), u2 = __shfl_up_sync(~0u, a3, 2), u3 = __shfl_up_sync(~0u, a3, 3);
            const uint32_t e4 = ((lane & 3) > 0 ? u1 : 0) + ((lane & 3) > 1 ? u2 : 0) + ((lane & 3) > 2 ? u3 : 0);
            const uint32_t w1 = __shfl_sync(~0u, e4 + a3, 3), w2 = __shfl_sync(~0u, e4 + a3, 7), w3 = __shfl_sync(~0u, e4 + a3, 11);
            const uint32_t ex = e4 + ((lane & 12) > 0 ? w1 : 0) + ((lane & 12) > 4 ? w2 : 0) + ((lane & 12) > 8 ? w3 : 0);
            const uint32_t ex4 = ex * 0x01010101u + (h.x << 8 | a1 << 16 | a2 << 24);
            #pragma unroll
            for (int i = 0; i < 2; i++) {
                pos[i] += __byte_perm(__shfl_sync(~0u, ex4, key[i] >> 2), 0, 0x4440 | (key[i] & 3));
                const int slot = __shfl_sync(~0u, myslot, pos[i] >> 3);
                sts8(sb + SM_ORD + slot * 8 + (pos[i] & 7), ht + 96 * i);
                if ((pos[i] & 7) == 0) sts32(sb + SM_GM + (63 - key[i] <= KS_ / 2 - 2 ? slot : 31) * 4, max(63 - key[i], 2));
            }
            __syncwarp();
            if (lane == 0) mbar_arrive(mbN);
            if (warp == 13 && elect()) load_w(sb + SM_W, &mapWu, 128, mbU);
        }
    } else {
        asm volatile("setmaxnreg.inc.sync.aligned.u32 160;");
        const int wg = warp >> 2, g = lane >> 2, t = lane & 3;
        {
            const uint32_t ed[8] = {d0.x, d0.y, d0.z, d0.w, d1.x, d1.y, d1.z, d1.w};
            const uint32_t es[8] = {s0.x, s0.y, s0.z, s0.w, s1.x, s1.y, s1.z, s1.w};
            uint32_t key[8], pos[8];
            #pragma unroll
            for (int j = 0; j < 8; j++) { key[j] = __umulhi(ed[j], 22605092u); pos[j] = 0; }
            #pragma unroll
            for (int j = 0; j < 4; j++) pos[j] = atoms_add(sb + SM_HIS + key[j] * 4, 1);
            if (v1) {
                #pragma unroll
                for (int j = 4; j < 8; j++) pos[j] = atoms_add(sb + SM_HIS + key[j] * 4, 1);
            }
            __syncwarp();
            bar_arrive(BAR_R, CT + 32);
            uint32_t m[8], nd[8], aw[8], ab[8], big = 0;
            #pragma unroll
            for (int j = 0; j < 8; j++) {
                m[j] = es[j] * 65536 + (tid * 32 + (j >> 2) * (CT * 32) + (j & 3) * 8);
                nd[j] = ed[j] - key[j] * TILE;
                const uint32_t u = __umulhi(pos[j], 0x15555556u);
                aw[j] = key[j] * 192 + pos[j] * 16 - u * 188;
                ab[j] = aw[j] - u * 3 + 12;
                big = max(big, pos[j]);
            }
            if (big >= LCAP) {
                #pragma unroll
                for (int j = 0; j < 8; j++)
                    if (pos[j] >= LCAP) {
                        aw[j] = NCTA * 192 + min(atoms_add(sb + SM_HIS + NCTA * 4 + (key[j] >> 8), 1), 31u) * 16;
                        ab[j] = aw[j] + 8;
                        sts32(sb + SM_L + aw[j] + 4, key[j]);
                    }
            }
            #pragma unroll
            for (int j = 0; j < 4; j++) { sts32(sb + SM_L + aw[j], m[j]); sts8(sb + SM_L + ab[j], nd[j]); }
            if (v1) {
                #pragma unroll
                for (int j = 4; j < 8; j++) { sts32(sb + SM_L + aw[j], m[j]); sts8(sb + SM_L + ab[j], nd[j]); }
            }
            __syncwarp();
            bar_arrive(BAR_STG, CT + 96);
        }

        {
            constexpr int NL = NF + (NCTA * 12 - NF * CT) / PW;
            static_assert(NF * CT + (NL - NF) * PW == NCTA * 12 && PW % 12 == 0, "layers");
            auto cell0 = [](int k) { return k < NF ? k * CT : NF * CT + (k - NF) * PW; };
            uint4 rec[NL];
            uint32_t tag;
            const uint4* lines = gRec + cta * (NCTA * 12) + tid;
            const uint32_t row = (warp * 16 + (lane & 15)) * 128 + (((lane >> 4) ^ (lane & 7)) << 4);
            uint32_t ax[32];
            auto fetch = [&]() {
                mbar_wait(mbR, 0);
                tag = lds32(sb + SM_GM + 116);
                #pragma unroll
                for (int k = NF; k < NL; k++) rec[k].w = tag;
                #pragma unroll
                for (int k = 0; k < NL; k++)
                    if (k < NF || tid < PW)
                        asm volatile("ld.relaxed.gpu.global.v4.u32 {%0,%1,%2,%3}, [%4];"
                            : "=r"(rec[k].x), "=r"(rec[k].y), "=r"(rec[k].z), "=r"(rec[k].w) : "l"(lines + cell0(k)) : "memory");
            };
            float dq[64];
            auto store_q = [&]() {
                uint32_t rq[32];
                #pragma unroll
                for (int i = 0; i < 32; i++) rq[i] = pack_bf16(dq[2 * i], dq[2 * i + 1]);
                mbar_wait(mbF + 16, 0);
                store_frag(sb + SM_Q, row, rq);
                __syncwarp();
                if (lane == 0) mbar_arrive(mbN);
            };
            {
                uint32_t r[32];
                float d[64];
                mbar_wait(mbX + 8 * wg, 0);
                load_frag(ax, sb + SM_X, row);
                mbar_wait(mbW1, 0);
                if (wg == 1) bar_sync(BAR_O, 256);
                gemm128<sb + SM_Q>(d, ax);
                if (wg == 0) bar_arrive(BAR_O, 256);
                wg_wait(d);
                #pragma unroll
                for (int i = 0; i < 32; i++) r[i] = pack_bf16(d[2 * i], d[2 * i + 1]);
                store_frag(sb, row + (wg == 2 ? SM_Q + 16384 : SM_X), r, wg == 2 ? 8192 : HALF);
                bar_arrive(BAR_P + wg, 160);
                mbar_wait(mbV, 0);
                gemm128<sb + SM_W + 32768>(d, ax);
                wg_wait(d);
                #pragma unroll
                for (int i = 0; i < 32; i++) r[i] = pack_half(d[2 * i], d[2 * i + 1]);
                if (wg < 2) mbar_wait(mbF + 8 * wg, 0);
                store_frag(sb + SM_X, row, r);
                fetch();
                mbar_wait(mbW2, 0);
                gemm128<sb + SM_W>(dq, ax);
            }
            wg_wait(dq);
            uint32_t any;
            #pragma unroll 1
            for (int it = 0;; it++) {
                any = 0;
                #pragma unroll
                for (int k = 0; k < NL; k++) any |= rec[k].w ^ tag;
                if (!__any_sync(~0u, any & 0x7f000000)) break;
                if (it > (1 << 20)) __trap();
                #pragma unroll
                for (int k = 0; k < NL; k++)
                    asm volatile("{.reg .pred p; setp.ne.u32 p, %5, 0; @p ld.relaxed.gpu.global.v4.u32 {%0,%1,%2,%3}, [%4];}"
                        : "+r"(rec[k].x), "+r"(rec[k].y), "+r"(rec[k].z), "+r"(rec[k].w) : "l"(lines + cell0(k)), "r"((rec[k].w ^ tag) & 0x7f000000) : "memory");
            }
            uint32_t todo = 0, more = __ballot_sync(~0u, (int)any < 0), from = 0;
            uint4 x;
            auto read_extra = [&]() {
                asm volatile("ld.relaxed.gpu.global.v4.u32 {%0,%1,%2,%3}, [%4];"
                    : "=r"(x.x), "=r"(x.y), "=r"(x.z), "=r"(x.w) : "l"(gRec + G_OVF + from * 32 + lane) : "memory");
            };
            auto next_extra = [&]() {
                const int b = __ffs(more) - 1;
                from = (warp * 32 + b + cell0(__ffs(__shfl_sync(~0u, todo, b)) - 1)) / 12;
                if (lane == b) todo &= todo - 1;
            };
            if (more) {
                #pragma unroll
                for (int k = 0; k < NL; k++) todo |= rec[k].w >> 31 << k;
                next_extra();
                read_extra();
            }
            const uint32_t eb = (tid / 12) * (CHUNK * 8);
            uint32_t at[3 * NL];
            auto count = [&](int k) {
                #pragma unroll
                for (int i = 0; i < 3; i++) at[3 * k + i] = atoms_add(sb + SM_CNT + __byte_perm(rec[k].w, 0, 0x4440 + i) * 4, 2);
            };
            auto list = [&](int k) {
                #pragma unroll
                for (int i = 0; i < 3; i++) {
                    const uint32_t v = i == 0 ? rec[k].x : i == 1 ? rec[k].y : rec[k].z;
                    sts64(sb + SM_L + tid * 24 + cell0(k) * 24 + i * 8, __byte_perm(v, 0, 0x4324), (v & 0x7ff8) + eb + cell0(k) / 12 * (CHUNK * 8));
                    sts16(at[3 * k + i], tid * 24 + cell0(k) * 24 + i * 8);
                }
            };
            #pragma unroll
            for (int k = 0; k < NF; k++) count(k);
            if (tid < PW) {
                #pragma unroll
                for (int k = NF; k < NL; k++) count(k);
            }
            __syncwarp();
            const bool late = more;
            if (!late) bar_arrive(BAR_N, CT + 96);
            #pragma unroll
            for (int k = 0; k < NF; k++) list(k);
            if (tid < PW) {
                #pragma unroll
                for (int k = NF; k < NL; k++) list(k);
            }
            __syncwarp();
            #pragma unroll 1
            for (int it = 0; more; it++) {
                if (!__any_sync(~0u, (x.w ^ tag) & 0x7f000000)) {
                    if ((int)x.w < 0) sts32(sb + SM_GM + 124, 1);
                    if (x.y == cta) {
                        const uint32_t i = min(atoms_add(sb + SM_GM + 112 + (x.x & 4), 1), XCAP - 1);
                        sts16(atoms_add(sb + SM_CNT + (x.z & 255) * 4, 2), L_X + i * 8);
                        sts64(sb + SM_L + L_X + i * 8, x.x >> 16 << 8, (x.x & 0x7ff8) + from * (CHUNK * 8));
                    }
                    more = __ballot_sync(~0u, todo);
                    if (!more) break;
                    next_extra();
                }
                if (it > (1 << 20)) __trap();
                read_extra();
            }
            __syncwarp();
            if (late) bar_arrive(BAR_N, CT + 96);
            store_q();
        }
        const uint32_t I = __shfl_sync(~0u, (g >> 1) == t ? ((g & 1) ? 0x3F000000u : 0x00003F00u) : 0u, lane);
        const uint64_t Pb = __shfl_sync(~0u, (unsigned long long)(gP + t * 16), lane);
        const uint64_t Eb = __shfl_sync(~0u, (unsigned long long)(ea + (t & 1) * 4), lane);
        const uint32_t msk = __shfl_sync(~0u, t < 2 ? ~0u : 0u, lane);
        int gi = (int)(((WARP_END << 5) >> (5 * warp)) & 31);
        const int gend = (int)((WARP_END >> (5 * warp)) & 31);
        sched_fence();
        mbar_wait(mbN, 0);
        uint32_t upar = 0;
        if (__builtin_expect(lds32(sb + SM_GM + 124) == 0 && lds32(sb + SM_GM + 112) <= XCAP, 1)) {
            float acc[32], Q[32], z[32], tt[32], y[4];
            const uint4 B0 = lds128(sb + SM_WF + lane * 16), B1 = lds128(sb + SM_WF + 512 + lane * 16);
            const uint32_t B[8] = {B0.x, B0.y, B0.z, B0.w, B1.x, B1.y, B1.z, B1.w};
            uint32_t rp = 0;
            uint4 p[2][4];
            uint64_t pa, pe;
            uint32_t ri, r0, r1, ev, e0, e1, qa;
            auto ldidx = [&]() { ri = lds16(rp); rp += 2; };
            auto ldrec = [&]() { asm volatile("ld.shared.v2.u32 {%0,%1}, [%2];" : "=r"(r0), "=r"(r1) : "r"(sb + SM_L + ri)); };
            auto addr = [&]() {
                asm volatile("mad.wide.u32 %0, %1, 1, %2;" : "=l"(pa) : "r"(r0), "l"(Pb));
                asm volatile("mad.wide.u32 %0, %1, 1, %2;" : "=l"(pe) : "r"(r1), "l"(Eb));
            };
            auto lde = [&]() { asm volatile("ld.global.nc.u32 %0, [%1];" : "=r"(ev) : "l"(pe)); };
            int cnt = 0;
            auto half = [&](int b) {
                #pragma unroll
                for (int k = 0; k < 32; k++) {
                    const int n = k >> 2;
                    if (k == 0) {
                        asm volatile("and.b32 %0, %1, %2;" : "=r"(e0) : "r"(ev), "r"(msk));
                        asm volatile("lop3.b32 %0, %1, %2, 0, 0x30;" : "=r"(e1) : "r"(ev), "r"(msk));
                    }
                    if ((k & 3) == 0) mma8(y, (n & 1) ? p[b][n >> 1].z : p[b][n >> 1].x, (n & 1) ? p[b][n >> 1].w : p[b][n >> 1].y, I, Q + 4 * n);
                    if ((k & 3) == M2) mma8(z + 4 * n, e0, e1, B[n], y);
                    if (k == KE) lde();
                    if (k >= KP && k < KP + 4 * KS && (k - KP) % KS == 0) p[1 - b][(k - KP) / KS] = ldg128((const char*)pa + (k - KP) / KS * 64);
                    if (k == KI) ldidx();
                    if (k == KR) ldrec();
                    if (k == KA) addr();
                    const int a = (k + 64 - LA) & 31, c = (k + 64 - LA - LB) & 31;
                    tt[a] = tanh_a(z[a]);
                    asm volatile("{.reg .f32 u; fma.rn.f32 u, %1, %2, %1; add.f32 %0, %0, u;}" : "+f"(acc[c]) : "f"(z[c]), "f"(tt[c]));
                    if ((k & 3) == 3 && k < 31) sched_fence();
                }
            };
            auto begin = [&]() {
                const int node = lds8(sb + SM_ORD + gi * 8 + g);
                qa = sb + SM_Q + node * 128 + ((t ^ (node & 7)) << 4);
                rp = sb + SM_K + node * KS_ + 4;
                cnt = lds32(sb + SM_GM + gi * 4);
                if (gi + 1 < gend) sts16(rp - 4 + (cnt + (t & 1)) * 2, lds16(sb + SM_K + lds8(sb + SM_ORD + gi * 8 + 8 + g) * KS_ + (t & 1) * 2));
                __syncwarp();
                const float zero[4] = {0.f, 0.f, 0.f, 0.f};
                #pragma unroll
                for (int q = 0; q < 4; q++) {
                    const uint4 v = lds128((qa ^ ((q & 1) << 6)) + (q >> 1) * HALF);
                    mma8(Q + 8 * q, v.x, v.y, I, zero);
                    mma8(Q + 8 * q + 4, v.z, v.w, I, zero);
                }
                #pragma unroll
                for (int i = 0; i < 32; i++) { acc[i] = 0.f; z[i] = 0.f; tt[i] = 0.f; }
            };
            auto finish = [&]() {
                #pragma unroll
                for (int i = 32 - LA - LB; i < 32; i++) acc[i] += i < 32 - LA ? fmaf(z[i], tt[i], z[i]) : silu_half(z[i]);
                #pragma unroll
                for (int q = 0; q < 4; q++)
                    sts128((qa ^ ((q & 1) << 6)) + (q >> 1) * HALF,
                           make_uint4(pack_half(acc[8 * q], acc[8 * q + 1]), pack_half(acc[8 * q + 2], acc[8 * q + 3]),
                                      pack_half(acc[8 * q + 4], acc[8 * q + 5]), pack_half(acc[8 * q + 6], acc[8 * q + 7])));
            };
            const uint32_t first = lds32(sb + SM_K + lds8(sb + SM_ORD + gi * 8 + g) * KS_);
            ri = first & 0xffff; ldrec(); addr();
            ri = first >> 16; ldrec(); lde();
            mbar_wait(mbB, 0);
            {
                uint32_t c0, c1;
                asm volatile("mov.u32 %0, %clock;" : "=r"(c0));
                do { asm volatile("mov.u32 %0, %clock;" : "=r"(c1)); } while (c1 - c0 < (uint32_t)((2 - wg) * STAG));
            }
            #pragma unroll
            for (int q = 0; q < 4; q++) p[0][q] = ldg128((const char*)pa + q * 64);
            addr();
            #pragma unroll 1
            while (true) {
                begin();
                #pragma unroll 1
                while (true) {
                    half(0);
                    if (cnt == 1) break;
                    half(1);
                    cnt -= 2;
                    if (cnt == 0) break;
                }
                finish();
                if (++gi == gend) break;
                if (cnt) {
                    #pragma unroll
                    for (int q = 0; q < 4; q++) p[0][q] = p[1][q];
                }
            }
        } else {
            float* agg = (float*)(smem + SM_W);
            mbar_wait(mbU, 0);
            bar_sync(BAR_C, CT);
            upar = 1;
            #pragma unroll 1
            for (int i = tid; i < 192 * 128 / 4; i += CT) ((float4*)agg)[i] = make_float4(0.f, 0.f, 0.f, 0.f);
            mbar_wait(mbB, 0);
            bar_sync(BAR_C, CT);
            float w3[4][4];
            #pragma unroll
            for (int k = 0; k < 4; k++)
                #pragma unroll
                for (int u = 0; u < 4; u++) w3[k][u] = __uint_as_float((uint32_t)__ldg(w3g + k * 128 + lane * 4 + u) << 16);
            #pragma unroll 1
            for (int e0 = warp * 32; e0 < N_EDGES; e0 += CT) {
                const uint32_t nl = __ldg((const int*)dst + e0 + lane) - node0;
                uint32_t hit = __ballot_sync(~0u, nl < TILE);
                #pragma unroll 1
                while (hit) {
                    const int b = __ffs(hit) - 1;
                    hit &= hit - 1;
                    const int n = __shfl_sync(~0u, nl, b);
                    const uint2 pv = __ldcg((const uint2*)(gP + __ldg((const int*)src + e0 + b) * 256 + lane * 8));
                    const uint2 e2 = __ldg((const uint2*)ea + e0 + b);
                    const uint2 qv = *(const uint2*)(smem + SM_Q + (lane >> 4) * HALF + n * 128 + ((((lane >> 1) & 7) ^ (n & 7)) << 4) + (lane & 1) * 8);
                    const float ev[4] = {__uint_as_float(e2.x << 16), __uint_as_float(e2.x & 0xffff0000u),
                                         __uint_as_float(e2.y << 16), __uint_as_float(e2.y & 0xffff0000u)};
                    float zz[4] = {__uint_as_float(pv.x << 16) + __uint_as_float(qv.x << 16),
                                   __uint_as_float(pv.x & 0xffff0000u) + __uint_as_float(qv.x & 0xffff0000u),
                                   __uint_as_float(pv.y << 16) + __uint_as_float(qv.y << 16),
                                   __uint_as_float(pv.y & 0xffff0000u) + __uint_as_float(qv.y & 0xffff0000u)};
                    #pragma unroll
                    for (int u = 0; u < 4; u++) {
                        #pragma unroll
                        for (int k = 0; k < 4; k++) zz[u] = fmaf(ev[k], w3[k][u], zz[u]);
                        atomicAdd(&agg[n * 128 + lane * 4 + u], silu_half(0.5f * zz[u]));
                    }
                }
            }
            bar_sync(BAR_C, CT);
            #pragma unroll 1
            for (int i = tid; i < 192 * 16; i += CT) {
                const int n = i >> 4, c = i & 15;
                const float* a = agg + n * 128 + c * 8;
                sts128(sb + SM_Q + (c >> 3) * HALF + n * 128 + (((c & 7) ^ (n & 7)) << 4),
                       make_uint4(pack_half(a[0], a[1]), pack_half(a[2], a[3]), pack_half(a[4], a[5]), pack_half(a[6], a[7])));
            }
            fence_async_smem();
            bar_sync(BAR_C, CT);
            if (warp == 0 && elect()) load_w(sb + SM_W, &mapWu, 128, mbU);
            __syncwarp();
        }

        {
            int tid3, cta3;
            asm volatile("mov.u32 %0, %tid.x; mov.u32 %1, %ctaid.x;" : "=r"(tid3), "=r"(cta3));
            const int lane3 = tid3 & 31, wrow3 = (tid3 >> 5) * 16;
            __syncwarp();
            if (lane3 == 0) mbar_arrive(mbG);
            const int row = wrow3 + (lane3 >> 3), c = lane3 & 7;
            const int nleft = min(TILE, N_NODES - cta3 * TILE) - row;
            uint4* o = out + (cta3 * TILE + row) * 16 + c;
            const uint32_t to = sb + SM_X + (wrow3 + (lane3 & 15)) * 128 + (((lane3 >> 4) ^ (lane3 & 7)) << 4);
            const uint32_t from = sb + SM_X + row * 128 + ((c ^ (row & 3)) << 4);
            float d[2][32];
            uint32_t ag[32];
            load_frag(ag, 0, to);
            #pragma unroll
            for (int i = 0; i < 32; i++)
                asm volatile("shl.b32 %0, %2, 16; and.b32 %1, %2, 0xffff0000;" : "=&f"(d[i >> 4][(2 * i) & 31]), "=f"(d[i >> 4][(2 * i + 1) & 31]) : "r"(ag[i]));
            sched_fence();
            mbar_wait(mbU, upar);
            mbar_wait(mbG, 0);
            const int turn = 2 - (tid3 >> 7);
            load_frag(ag, SM_Q - SM_X, to);
            if (turn) bar_sync(BAR_T - 1 + turn, 256);
            wg_fence();
            gemm64<sb + SM_W>(d[0], ag);
            gemm64<sb + SM_W + 16384>(d[1], ag);
            if (turn < 2) bar_arrive(BAR_T + turn, 256);
            #pragma unroll
            for (int h = 0; h < 2; h++) {
                if (h == 0) wg_wait32<1>(d[0]); else wg_wait32<0>(d[1]);
                float tq[32];
                #pragma unroll
                for (int j = 0; j < 5; j++) {
                    if (j < 4) {
                        #pragma unroll
                        for (int i = 8 * j; i < 8 * j + 8; i++) tq[i] = tanh_a(d[h][i]);
                    }
                    if (j >= 1) {
                        uint32_t r[4];
                        #pragma unroll
                        for (int i = 0; i < 4; i++) {
                            const int k = 8 * j - 8 + 2 * i;
                            r[i] = pack_bf16(fmaf(d[h][k], tq[k], d[h][k]), fmaf(d[h][k + 1], tq[k + 1], d[h][k + 1]));
                        }
                        asm volatile("stmatrix.sync.aligned.m8n8.x4.shared.b16 [%0], {%1,%2,%3,%4};"
                            :: "r"((to ^ ((j - 1) << 5)) + h * HALF), "r"(r[0]), "r"(r[1]), "r"(r[2]), "r"(r[3]) : "memory");
                    }
                }
                __syncwarp();
                uint4 v[4];
                #pragma unroll
                for (int i = 0; i < 4; i++) v[i] = lds128((from ^ ((i & 1) << 6)) + i * 512 + h * HALF);
                #pragma unroll
                for (int i = 0; i < 4; i++)
                    asm volatile("{.reg .pred p; setp.lt.s32 p, %5, %6; @p st.global.v4.u32 [%0], {%1,%2,%3,%4};}"
                        :: "l"(o + i * 64 + h * 8), "r"(v[i].x), "r"(v[i].y), "r"(v[i].z), "r"(v[i].w), "r"(4 * i), "r"(nleft) : "memory");
            }
        }
    }
}

__device__ float g_agg[N_NODES * 128];
__global__ void plain_zero() {
    for (int i = blockIdx.x * blockDim.x + threadIdx.x; i < N_NODES * 128; i += gridDim.x * blockDim.x) g_agg[i] = 0.f;
}
__global__ void plain_edge(const __nv_bfloat16* x, const __nv_bfloat16* ea, const int* src, const int* dst, const __nv_bfloat16* w) {
    __shared__ float m[260];
    const int e = blockIdx.x, c = threadIdx.x;
    m[c] = __bfloat162float(x[src[e] * 128 + c]);
    m[128 + c] = __bfloat162float(x[dst[e] * 128 + c]);
    if (c < 4) m[256 + c] = __bfloat162float(ea[e * 4 + c]);
    __syncthreads();
    float z = 0.f;
    for (int k = 0; k < 260; k++) z = fmaf(m[k], __bfloat162float(w[k * 128 + c]), z);
    atomicAdd(&g_agg[dst[e] * 128 + c], silu_half(0.5f * z));
}
__global__ void plain_node(const __nv_bfloat16* x, const __nv_bfloat16* w, __nv_bfloat16* out) {
    __shared__ float m[256];
    const int n = blockIdx.x, c = threadIdx.x;
    m[c] = __bfloat162float(x[n * 128 + c]);
    m[128 + c] = g_agg[n * 128 + c];
    __syncthreads();
    float z = 0.f;
    for (int k = 0; k < 256; k++) z = fmaf(m[k], __bfloat162float(w[k * 128 + c]), z);
    out[n * 128 + c] = __float2bfloat16(silu_half(0.5f * z));
}

typedef CUresult (*EncodeFn)(CUtensorMap*, CUtensorMapDataType, cuuint32_t, void*, const cuuint64_t*, const cuuint64_t*,
                             const cuuint32_t*, const cuuint32_t*, CUtensorMapInterleave, CUtensorMapSwizzle,
                             CUtensorMapL2promotion, CUtensorMapFloatOOBfill);

void make_line_map(EncodeFn fn, CUtensorMap* m, const void* base, int words) {
    cuuint64_t dims[2] = {(cuuint64_t)NCTA * words, NCTA};
    cuuint64_t strides[1] = {(cuuint64_t)NCTA * words * 4};
    cuuint32_t box[2] = {(cuuint32_t)words, NCTA};
    cuuint32_t es[2] = {1, 1};
    fn(m, CU_TENSOR_MAP_DATA_TYPE_UINT32, 2, (void*)base, dims, strides, box, es, CU_TENSOR_MAP_INTERLEAVE_NONE,
       CU_TENSOR_MAP_SWIZZLE_NONE, CU_TENSOR_MAP_L2_PROMOTION_NONE, CU_TENSOR_MAP_FLOAT_OOB_FILL_NONE);
}

void make_map(EncodeFn fn, CUtensorMap* m, const void* base, int rows, int box_rows) {
    cuuint64_t dims[2] = {128, (cuuint64_t)rows};
    cuuint64_t strides[1] = {256};
    cuuint32_t box[2] = {64, (cuuint32_t)box_rows};
    cuuint32_t es[2] = {1, 1};
    fn(m, CU_TENSOR_MAP_DATA_TYPE_BFLOAT16, 2, (void*)base, dims, strides, box, es, CU_TENSOR_MAP_INTERLEAVE_NONE,
       CU_TENSOR_MAP_SWIZZLE_128B, CU_TENSOR_MAP_L2_PROMOTION_L2_256B, CU_TENSOR_MAP_FLOAT_OOB_FILL_NONE);
}

}

extern "C" void kernel_launch(void* const* d_in, const int* in_sizes, int n_in, void* d_out, int out_size) {
    (void)in_sizes; (void)n_in; (void)out_size;
    static int mode = 0;
    static EncodeFn fn = nullptr;
    static void *p_P, *p_rec, *p_bar;
    if (!mode) {
        void* p = nullptr;
        cudaDriverEntryPointQueryResult qr;
        cudaGetDriverEntryPoint("cuTensorMapEncodeTiled", &p, cudaEnableDefault, &qr);
        fn = (EncodeFn)p;
        cudaGetSymbolAddress(&p_P, g_P);
        cudaGetSymbolAddress(&p_rec, g_rec);
        cudaGetSymbolAddress(&p_bar, g_bar);
        int dev = 0, sms = 0, per_sm = 0;
        cudaGetDevice(&dev);
        cudaDeviceGetAttribute(&sms, cudaDevAttrMultiProcessorCount, dev);
        if (cudaFuncSetAttribute(mpnn_kernel, cudaFuncAttributeMaxDynamicSharedMemorySize, SM_TOTAL) == cudaSuccess)
            cudaOccupancyMaxActiveBlocksPerMultiprocessor(&per_sm, mpnn_kernel, THREADS, SM_TOTAL);
        (void)cudaGetLastError();
        mode = fn && sms * per_sm >= NCTA ? 1 : 2;
    }
    if (mode == 2) {
        plain_zero<<<512, 256, 0, cudaStreamPerThread>>>();
        plain_edge<<<N_EDGES, 128, 0, cudaStreamPerThread>>>((const __nv_bfloat16*)d_in[0], (const __nv_bfloat16*)d_in[1], (const int*)d_in[2], (const int*)d_in[3],
                                     (const __nv_bfloat16*)d_in[4]);
        plain_node<<<N_NODES, 128, 0, cudaStreamPerThread>>>((const __nv_bfloat16*)d_in[0], (const __nv_bfloat16*)d_in[5], (__nv_bfloat16*)d_out);
        return;
    }
    CUtensorMap mx, mp, mm, mu, ml;
    make_line_map(fn, &ml, p_rec, 48);
    make_map(fn, &mx, d_in[0], N_NODES, 64);
    make_map(fn, &mp, p_P, N_NODES, 64);
    make_map(fn, &mm, d_in[4], 260, 128);
    make_map(fn, &mu, d_in[5], 256, 128);
    cudaLaunchConfig_t cfg = {};
    cfg.gridDim = dim3(NCTA); cfg.blockDim = dim3(THREADS); cfg.dynamicSmemBytes = SM_TOTAL; cfg.stream = cudaStreamPerThread;
    cudaLaunchAttribute at; at.id = cudaLaunchAttributeCooperative; at.val.cooperative = 1;
    cfg.attrs = &at; cfg.numAttrs = 1;
    cudaLaunchKernelEx(&cfg, mpnn_kernel, (const int4*)d_in[3], (const int4*)d_in[2], (const char*)d_in[1],
                       (const unsigned short*)d_in[4] + 256 * 128, (uint4*)d_out,
                       (char*)p_P, (uint4*)p_rec, (uint32_t*)p_bar, mx, mp, mm, mu, ml);
}
```
